```python
import torch

def _softmax(x, axis=-1):
    return torch.softmax(x, dim=axis)
def _gelu(x):
    return torch.nn.functional.gelu(x, approximate="tanh")
def _silu(x):
    return torch.nn.functional.silu(x)
def _sigmoid(x):
    return torch.sigmoid(x)
def _layernorm(x, axis=-1, eps=1e-5):
    m = x.mean(dim=axis, keepdim=True)
    v = x.var(dim=axis, keepdim=True, unbiased=False)
    return (x - m) / torch.sqrt(v + eps)
def _scatter_add(tgt, idx, src, axis=0):
    return tgt.clone().index_add_(axis, idx, src)
def _segment_sum(src, seg, n):
    out = torch.zeros((n,) + src.shape[1:], dtype=src.dtype)
    return out.index_add_(0, seg, src)
def _pad(x, pw):
    flat = tuple(v for pair in reversed(pw) for v in pair)
    return torch.nn.functional.pad(x, flat)

kernel_name = 'recurrent_scan__spectral_gfnet__mixer_token_mlp__prompt'

def setup_inputs():

    _w = (lambda a: (lambda t: t.to(torch.bfloat16) if t.is_floating_point() else t)(torch.as_tensor(a)))
    def _A_setup():
        B, S, D = 1, 2048, 512
        Df = D // 2 + 1
        return {
            "x": _w((lambda *s: torch.randn(*s, dtype=torch.bfloat16) * 0.05)(B, S, D)),
            "w_r": _w((lambda *s: torch.randn(*s, dtype=torch.bfloat16) * 0.8)(S, Df) * 0.02),
            "w_i": _w((lambda *s: torch.randn(*s, dtype=torch.bfloat16) * 0.8)(S, Df) * 0.02),
        }
    _A_in = _A_setup()

    def _B_setup():
        B, S, D, F = 1, 2048, 512, 1792
        return {
            "x": _w((lambda *s: torch.randn(*s, dtype=torch.bfloat16) * 0.05)(B, S, D)),
            "w1": _w((lambda *s: torch.randn(*s, dtype=torch.bfloat16) * 1.6)(S, F) * (S ** -0.5)),
            "b1": _w((lambda *s: torch.randn(*s, dtype=torch.bfloat16) * 12.8)(F) * 0.02),
            "w2": _w((lambda *s: torch.randn(*s, dtype=torch.bfloat16) * 0.4)(F, S) * (F ** -0.5)),
            "b2": _w((lambda *s: torch.randn(*s, dtype=torch.bfloat16) * 6.4)(S) * 0.02),
        }
    _B_in = _B_setup()

    return {
        "A_x": _A_in["x"],
        "A_w_r": _A_in["w_r"],
        "A_w_i": _A_in["w_i"],
        "B_x": _B_in["x"],
        "B_w1": _B_in["w1"],
        "B_b1": _B_in["b1"],
        "B_w2": _B_in["w2"],
        "B_b2": _B_in["b2"],
    }

def reference(A_x, A_w_r, A_w_i, B_x, B_w1, B_b1, B_w2, B_b2):
    def _A_ref(x, w_r, w_i):
        B, S, D = x.shape
        X = (lambda x, axes=(-2,-1): torch.fft.rfft2(x.float(), dim=axes))(x, axes=(-2, -1))
        W = w_r + 1j * w_i
        X = X * W
        y = (lambda x, s, axes=(-2,-1): torch.fft.irfft2(x, s=s, dim=axes).to(torch.bfloat16))(X, (S, D), axes=(-2, -1))
        return y

    def _B_ref(x, w1, b1, w2, b2):
        B, S, D = x.shape
        h = _layernorm(x, axis=-1)
        u = torch.einsum("bsd,sf->bdf", h, w1) + b1
        u = _gelu(u)
        y = torch.einsum("bdf,fs->bds", u, w2) + b2
        return (lambda x, *d: x.permute(*d))(y, 0, 2, 1)

    x = A_x
    xn = _layernorm(x, axis=-1)
    s = _A_ref(xn, A_w_r, A_w_i)
    g = _silu(_B_ref(xn, B_w1, B_b1, B_w2, B_b2))
    return x + s * g
```

```cpp
#include <cuda_runtime.h>
#include <cuda_bf16.h>
#include <cuda_fp16.h>
#include <cuda.h>
#include <stdint.h>

#define TV(i, d) (d)
#define TUNE_PARAM
#define TUNE_ARG
#define GATE_W2 TV(0, 1)
#define T_PF    TV(1, 1500)
#define SLOT_PF TV(2, 350)
#define N_PF    TV(3, 4)
#define T_WK    TV(4, 1500)
#define W_AHEAD (spare ? TV(22, 8) : TV(7, 6))
#define WKY     TV(12, 300)
#define PACE_B  TV(5, 400)
#define NB_EARLY TV(6, 3)
#define PACE_F  TV(8, 200)
#define PACE_ST TV(9, 250)
#define B_OFS   TV(10, 100)
#define LAG2    TV(11, 0)
#define T_XB    TV(16, 500)
#define ONE_H   TV(18, 1)
#define B_GATE  TV(19, 1)
#define NSP     TV(20, 9)
#define LAG1    TV(21, 0)
#define ONE_U   TV(23, 0)
#define WEAK    TV(13, 0)
#define T_Y     TV(14, 1500)
#define PACE_Z  TV(15, 150)
#define NW2     TV(17, 99)
#define DRY 0
#define NH 2
namespace {

constexpr int SA = 6, SB = 6, SLOT = 16384;
constexpr int OFF_A = 0, OFF_B = SA * SLOT, OFF_X = (SA + SB) * SLOT, OFF_BAR = OFF_X + 32768;
constexpr int OFF_PIN = OFF_BAR + 576, SMEM_BYTES = OFF_BAR + 1280;
constexpr int BAR_FA = 0, BAR_EA = SA, BAR_FB = 2 * SA, BAR_EB = 2 * SA + SB, BAR_XC = 2 * SA + 2 * SB;
constexpr int BAR_FR = BAR_XC + 8, BAR_GO = BAR_FR + 1, BAR_UG = BAR_GO + 1, BAR_WD = BAR_UG + 1, BAR_WI = BAR_WD + 1, BAR_YR = BAR_WI + 1, BAR_HF = BAR_YR + 1, BAR_HA = BAR_HF + 1, BAR_XT = BAR_HA + 1, NBAR = BAR_XT + 1, BAR_RF = NBAR, BAR_RD = BAR_RF + 12;
constexpr int XB = 16384, OFF_FR = OFF_X + 17408, WIMG = 17408;
constexpr int IA_Y = 16, IA_C0 = 17, IA_C1 = 18;
constexpr int IA_W = 19, IA_U = 20, IA_C = 34, NA = 38;
constexpr int IB_W2 = 16, IB_Z = 30;
constexpr int YPITCH = 16512;
constexpr int CNT_H = 0, CNT_Y = 128, CNT_U = 160, CNT_Z = 416, CNT_DONE = 448, CNT_W = 480, CNT_T = 512, CNT_V = 544, CNT_WORDS = 800;

struct __align__(1024) Scratch {
    __nv_bfloat16 h[2048 * 512];
    __nv_bfloat16 Z[2 * 256 * 2048];
    __nv_bfloat16 u[512 * 1792];
    __nv_bfloat16 C[2 * 256 * 256];
    uint16_t T[4 * 4096];
    __half Y[128 * YPITCH];
    unsigned cnt[CNT_WORDS];
};
__device__ Scratch g_s;
#define STAMP(i) do {} while (0)

struct Maps { CUtensorMap w1, h, ys, ws, wr, wi, y, w2, ul, c, z, x, o; };

__device__ __forceinline__ void mbar_init(uint32_t bar, int cnt) { asm volatile("mbarrier.init.shared::cta.b64 [%0], %1;" :: "r"(bar), "r"(cnt)); }
__device__ __forceinline__ void mbar_expect(uint32_t bar, uint32_t bytes) { asm volatile("mbarrier.arrive.expect_tx.shared::cta.b64 _, [%0], %1;" :: "r"(bar), "r"(bytes) : "memory"); }
__device__ __forceinline__ void mbar_wait(uint32_t bar, uint32_t parity) {
    asm volatile("{.reg .pred p; .reg .u32 it; mov.u32 it, 0;\n"
      "W: mbarrier.try_wait.parity.shared::cta.b64 p, [%0], %1;\n"
      "@p bra D; add.u32 it, it, 1; setp.lt.u32 p, it, 400000; @p bra W; trap;\n D: }" :: "r"(bar), "r"(parity) : "memory");
}
__device__ __forceinline__ void mbar_arrive_p(uint32_t bar, bool p) {
    asm volatile("{.reg .pred q; setp.ne.u32 q, %1, 0; @q mbarrier.arrive.shared::cta.b64 _, [%0];}" :: "r"(bar), "r"((uint32_t)p) : "memory");
}
__device__ __forceinline__ void tma2d(uint32_t dst, const CUtensorMap* tm, uint32_t bar, int x, int y) {
    asm volatile("cp.async.bulk.tensor.2d.shared::cluster.global.mbarrier::complete_tx::bytes [%0], [%1, {%3, %4}], [%2];" :: "r"(dst), "l"(tm), "r"(bar), "r"(x), "r"(y) : "memory");
}
__device__ __forceinline__ void tma3d(uint32_t dst, const CUtensorMap* tm, uint32_t bar, int x, int y, int z) {
    asm volatile("cp.async.bulk.tensor.3d.shared::cluster.global.mbarrier::complete_tx::bytes [%0], [%1, {%3, %4, %5}], [%2];" :: "r"(dst), "l"(tm), "r"(bar), "r"(x), "r"(y), "r"(z) : "memory");
}
__device__ __forceinline__ void tma4d(uint32_t dst, const CUtensorMap* tm, uint32_t bar, int x, int y, int z, int w) {
    asm volatile("cp.async.bulk.tensor.4d.shared::cluster.global.mbarrier::complete_tx::bytes [%0], [%1, {%3, %4, %5, %6}], [%2];" :: "r"(dst), "l"(tm), "r"(bar), "r"(x), "r"(y), "r"(z), "r"(w) : "memory");
}
__device__ __forceinline__ void bulk1d(uint32_t dst, const void* src, uint32_t bytes, uint32_t bar) {
    asm volatile("cp.async.bulk.shared::cluster.global.mbarrier::complete_tx::bytes [%0], [%1], %2, [%3];" :: "r"(dst), "l"(src), "r"(bytes), "r"(bar) : "memory");
}
__device__ __forceinline__ void tma2d_pf(const CUtensorMap* tm, int x, int y) {
    asm volatile("cp.async.bulk.prefetch.tensor.2d.L2.global [%0, {%1, %2}];" :: "l"(tm), "r"(x), "r"(y) : "memory");
}
__device__ __forceinline__ void bulk_pf(const void* p, uint32_t bytes) { asm volatile("cp.async.bulk.prefetch.L2.global [%0], %1;" :: "l"(p), "r"(bytes) : "memory"); }
__device__ __forceinline__ void tma2d_st(const CUtensorMap* tm, uint32_t src, int x, int y) {
    asm volatile("cp.async.bulk.tensor.2d.global.shared::cta.bulk_group [%0, {%2, %3}], [%1];" :: "l"(tm), "r"(src), "r"(x), "r"(y) : "memory");
}
__device__ __forceinline__ void tma3d_st(const CUtensorMap* tm, uint32_t src, int x, int y, int z) {
    asm volatile("cp.async.bulk.tensor.3d.global.shared::cta.bulk_group [%0, {%2, %3, %4}], [%1];" :: "l"(tm), "r"(src), "r"(x), "r"(y), "r"(z) : "memory");
}
__device__ __forceinline__ void poll_ge(unsigned* p, unsigned target) {
    unsigned v; int it = 0;
    do { asm volatile("ld.relaxed.gpu.global.u32 %0, [%1];" : "=r"(v) : "l"(p) : "memory"); if (++it > 2000000) __trap(); } while (v < target);
    asm volatile("fence.acquire.gpu;" ::: "memory");
    asm volatile("fence.proxy.async.global;" ::: "memory");
}
__device__ __forceinline__ void red_release(unsigned* p, int weak = 0) {
    if (weak) asm volatile("red.relaxed.gpu.global.add.u32 [%0], 1;" :: "l"(p) : "memory");
    else asm volatile("red.release.gpu.global.add.u32 [%0], 1;" :: "l"(p) : "memory");
}
__device__ __forceinline__ bool elect() { uint32_t p; asm volatile("{.reg .pred q; elect.sync _|q, 0xffffffff; selp.u32 %0, 1, 0, q;}" : "=r"(p)); return p; }
__device__ __forceinline__ uint32_t clk() { uint32_t c; asm volatile("mov.u32 %0, %%clock;" : "=r"(c)); return c; }
__device__ __forceinline__ void wait_until(uint32_t t0, uint32_t d) { while (clk() - t0 < d) {} }
__device__ __forceinline__ void sts32(uint32_t a, uint32_t x) { asm volatile("st.shared.u32 [%0], %1;" :: "r"(a), "r"(x) : "memory"); }
__device__ __forceinline__ void bar_sync(int id, int n) { asm volatile("bar.sync %0, %1;" :: "r"(id), "r"(n) : "memory"); }
__device__ __forceinline__ void bar_arrive(int id, int n) { asm volatile("bar.arrive %0, %1;" :: "r"(id), "r"(n) : "memory"); }
__device__ __forceinline__ void wg_fence() { asm volatile("wgmma.fence.sync.aligned;" ::: "memory"); }
__device__ __forceinline__ void wg_commit() { asm volatile("wgmma.commit_group.sync.aligned;" ::: "memory"); }
template <int N> __device__ __forceinline__ void wg_wait() { asm volatile("wgmma.wait_group.sync.aligned %0;" :: "n"(N) : "memory"); }
template <int N> __device__ __forceinline__ void pin(float (&a)[N]) {
#pragma unroll
    for (int i = 0; i < N; i++) asm volatile("" : "+f"(a[i]) :: "memory");
}
template <int O, int C, int N> __device__ __forceinline__ void pin_r(float (&a)[N]) {
#pragma unroll
    for (int i = O; i < O + C; i++) asm volatile("" : "+f"(a[i]) :: "memory");
}
__device__ __forceinline__ uint32_t pk_h(float lo, float hi) { uint32_t r; asm("cvt.rn.f16x2.f32 %0, %1, %2;" : "=r"(r) : "f"(hi), "f"(lo)); return r; }
__device__ __forceinline__ uint32_t pk_b(float lo, float hi) { uint32_t r; asm("cvt.rn.bf16x2.f32 %0, %1, %2;" : "=r"(r) : "f"(hi), "f"(lo)); return r; }
__device__ __forceinline__ float bf_lo(uint32_t v) { return __uint_as_float(v << 16); }
__device__ __forceinline__ float bf_hi(uint32_t v) { return __uint_as_float(v & 0xffff0000u); }
__device__ __forceinline__ float rsqrt_fast(float x) { float r; asm("rsqrt.approx.ftz.f32 %0, %1;" : "=f"(r) : "f"(x)); return r; }
__device__ __forceinline__ float tanh_fast(float x) { float r; asm("tanh.approx.f32 %0, %1;" : "=f"(r) : "f"(x)); return r; }
__device__ __forceinline__ float cos2048(int a) { return __cosf((float)(((a + 1024) & 2047) - 1024) * 3.0679615757712823e-3f); }
__device__ __forceinline__ void mma_h(float (&d)[4], uint32_t a0, uint32_t a1, uint32_t a2, uint32_t a3, uint32_t b0, uint32_t b1) {
    asm("mma.sync.aligned.m16n8k16.row.col.f32.f16.f16.f32 {%0,%1,%2,%3}, {%4,%5,%6,%7}, {%8,%9}, {%0,%1,%2,%3};"
        : "+f"(d[0]), "+f"(d[1]), "+f"(d[2]), "+f"(d[3]) : "r"(a0), "r"(a1), "r"(a2), "r"(a3), "r"(b0), "r"(b1));
}
__device__ __forceinline__ void mma_b(float (&d)[4], uint32_t a0, uint32_t a1, uint32_t a2, uint32_t a3, uint32_t b0, uint32_t b1) {
    asm("mma.sync.aligned.m16n8k16.row.col.f32.bf16.bf16.f32 {%0,%1,%2,%3}, {%4,%5,%6,%7}, {%8,%9}, {%0,%1,%2,%3};"
        : "+f"(d[0]), "+f"(d[1]), "+f"(d[2]), "+f"(d[3]) : "r"(a0), "r"(a1), "r"(a2), "r"(a3), "r"(b0), "r"(b1));
}
__device__ __forceinline__ uint32_t fma_b2(uint32_t a, uint32_t b, uint32_t c) { uint32_t r; asm("fma.rn.bf16x2 %0, %1, %2, %3;" : "=r"(r) : "r"(a), "r"(b), "r"(c)); return r; }
__device__ __forceinline__ void stsm4(uint32_t a, uint32_t r0, uint32_t r1, uint32_t r2, uint32_t r3) {
    asm volatile("stmatrix.sync.aligned.m8n8.x4.shared.b16 [%0], {%1,%2,%3,%4};" :: "r"(a), "r"(r0), "r"(r1), "r"(r2), "r"(r3) : "memory");
}
__device__ __forceinline__ void stsm4t(uint32_t a, uint32_t r0, uint32_t r1, uint32_t r2, uint32_t r3) {
    asm volatile("stmatrix.sync.aligned.m8n8.x4.trans.shared.b16 [%0], {%1,%2,%3,%4};" :: "r"(a), "r"(r0), "r"(r1), "r"(r2), "r"(r3) : "memory");
}
__device__ __forceinline__ void ldsm4t(uint32_t a, uint32_t& r0, uint32_t& r1, uint32_t& r2, uint32_t& r3) {
    asm volatile("ldmatrix.sync.aligned.m8n8.x4.trans.shared.b16 {%0,%1,%2,%3}, [%4];" : "=r"(r0), "=r"(r1), "=r"(r2), "=r"(r3) : "r"(a) : "memory");
}
__device__ __forceinline__ void st_async4(uint32_t a, uint32_t v0, uint32_t v1, uint32_t v2, uint32_t v3, uint32_t bar) {
    asm volatile("st.async.weak.shared::cluster.mbarrier::complete_tx::bytes.v4.b32 [%0], {%1,%2,%3,%4}, [%5];" :: "r"(a), "r"(v0), "r"(v1), "r"(v2), "r"(v3), "r"(bar) : "memory");
}
__device__ __forceinline__ float4 lds128f(uint32_t a) { float4 v; asm volatile("ld.shared.v4.f32 {%0,%1,%2,%3}, [%4];" : "=f"(v.x), "=f"(v.y), "=f"(v.z), "=f"(v.w) : "r"(a) : "memory"); return v; }
__device__ __forceinline__ uint4 lds128(uint32_t a) { uint4 v; asm volatile("ld.shared.v4.u32 {%0,%1,%2,%3}, [%4];" : "=r"(v.x), "=r"(v.y), "=r"(v.z), "=r"(v.w) : "r"(a) : "memory"); return v; }
__device__ __forceinline__ uint2 lds64(uint32_t a) { uint2 v; asm volatile("ld.shared.v2.u32 {%0,%1}, [%2];" : "=r"(v.x), "=r"(v.y) : "r"(a) : "memory"); return v; }
__device__ __forceinline__ uint32_t lds32(uint32_t a) { uint32_t v; asm volatile("ld.shared.u32 %0, [%1];" : "=r"(v) : "r"(a) : "memory"); return v; }
__device__ __forceinline__ void sts128(uint32_t a, uint32_t x, uint32_t y, uint32_t z, uint32_t w) { asm volatile("st.shared.v4.u32 [%0], {%1,%2,%3,%4};" :: "r"(a), "r"(x), "r"(y), "r"(z), "r"(w) : "memory"); }
__device__ __forceinline__ void sts128f(uint32_t a, float x, float y, float z, float w) { asm volatile("st.shared.v4.f32 [%0], {%1,%2,%3,%4};" :: "r"(a), "f"(x), "f"(y), "f"(z), "f"(w) : "memory"); }
__device__ __forceinline__ void sts64(uint32_t a, uint32_t x, uint32_t y) { asm volatile("st.shared.v2.u32 [%0], {%1,%2};" :: "r"(a), "r"(x), "r"(y) : "memory"); }
__device__ __forceinline__ uint4 ldg128_cg(const void* p) { uint4 v; asm volatile("ld.global.cg.v4.u32 {%0,%1,%2,%3}, [%4];" : "=r"(v.x), "=r"(v.y), "=r"(v.z), "=r"(v.w) : "l"(p) : "memory"); return v; }

template <int TB> __device__ __forceinline__ void wgmma_rs_bf16_n32(float (&d)[16], uint32_t a0, uint32_t a1, uint32_t a2, uint32_t a3, uint64_t db, int scale_d) {
    asm volatile("{.reg .pred p; setp.ne.b32 p, %21, 0;\n"
        "wgmma.mma_async.sync.aligned.m64n32k16.f32.bf16.bf16 {%0,%1,%2,%3,%4,%5,%6,%7,%8,%9,%10,%11,%12,%13,%14,%15}, {%16,%17,%18,%19}, %20, p, 1, 1, %22;}"
        : "+f"(d[0]), "+f"(d[1]), "+f"(d[2]), "+f"(d[3]), "+f"(d[4]), "+f"(d[5]), "+f"(d[6]), "+f"(d[7]), "+f"(d[8]), "+f"(d[9]), "+f"(d[10]), "+f"(d[11]), "+f"(d[12]), "+f"(d[13]), "+f"(d[14]), "+f"(d[15])
        : "r"(a0), "r"(a1), "r"(a2), "r"(a3), "l"(db), "r"(scale_d), "n"(TB));
}
template <int TB> __device__ __forceinline__ void wgmma_rs_f16_n32(float (&d)[16], uint32_t a0, uint32_t a1, uint32_t a2, uint32_t a3, uint64_t db, int scale_d) {
    asm volatile("{.reg .pred p; setp.ne.b32 p, %21, 0;\n"
        "wgmma.mma_async.sync.aligned.m64n32k16.f32.f16.f16 {%0,%1,%2,%3,%4,%5,%6,%7,%8,%9,%10,%11,%12,%13,%14,%15}, {%16,%17,%18,%19}, %20, p, 1, 1, %22;}"
        : "+f"(d[0]), "+f"(d[1]), "+f"(d[2]), "+f"(d[3]), "+f"(d[4]), "+f"(d[5]), "+f"(d[6]), "+f"(d[7]), "+f"(d[8]), "+f"(d[9]), "+f"(d[10]), "+f"(d[11]), "+f"(d[12]), "+f"(d[13]), "+f"(d[14]), "+f"(d[15])
        : "r"(a0), "r"(a1), "r"(a2), "r"(a3), "l"(db), "r"(scale_d), "n"(TB));
}
template <int TA, int TB, int O = 0, int NR> __device__ __forceinline__ void wgmma_ss_bf16_n128(float (&d)[NR], uint64_t da, uint64_t db, int scale_d) {
    asm volatile("{.reg .pred p; setp.ne.b32 p, %66, 0;\n"
        "wgmma.mma_async.sync.aligned.m64n128k16.f32.bf16.bf16 {%0,%1,%2,%3,%4,%5,%6,%7,%8,%9,%10,%11,%12,%13,%14,%15,%16,%17,%18,%19,%20,%21,%22,%23,%24,%25,%26,%27,%28,%29,%30,%31,%32,%33,%34,%35,%36,%37,%38,%39,%40,%41,%42,%43,%44,%45,%46,%47,%48,%49,%50,%51,%52,%53,%54,%55,%56,%57,%58,%59,%60,%61,%62,%63}, %64, %65, p, 1, 1, %67, %68;}"
        : "+f"(d[O + 0]), "+f"(d[O + 1]), "+f"(d[O + 2]), "+f"(d[O + 3]), "+f"(d[O + 4]), "+f"(d[O + 5]), "+f"(d[O + 6]), "+f"(d[O + 7]), "+f"(d[O + 8]), "+f"(d[O + 9]), "+f"(d[O + 10]), "+f"(d[O + 11]), "+f"(d[O + 12]), "+f"(d[O + 13]), "+f"(d[O + 14]), "+f"(d[O + 15]), "+f"(d[O + 16]), "+f"(d[O + 17]), "+f"(d[O + 18]), "+f"(d[O + 19]), "+f"(d[O + 20]), "+f"(d[O + 21]), "+f"(d[O + 22]), "+f"(d[O + 23]), "+f"(d[O + 24]), "+f"(d[O + 25]), "+f"(d[O + 26]), "+f"(d[O + 27]), "+f"(d[O + 28]), "+f"(d[O + 29]), "+f"(d[O + 30]), "+f"(d[O + 31]), "+f"(d[O + 32]), "+f"(d[O + 33]), "+f"(d[O + 34]), "+f"(d[O + 35]), "+f"(d[O + 36]), "+f"(d[O + 37]), "+f"(d[O + 38]), "+f"(d[O + 39]), "+f"(d[O + 40]), "+f"(d[O + 41]), "+f"(d[O + 42]), "+f"(d[O + 43]), "+f"(d[O + 44]), "+f"(d[O + 45]), "+f"(d[O + 46]), "+f"(d[O + 47]), "+f"(d[O + 48]), "+f"(d[O + 49]), "+f"(d[O + 50]), "+f"(d[O + 51]), "+f"(d[O + 52]), "+f"(d[O + 53]), "+f"(d[O + 54]), "+f"(d[O + 55]), "+f"(d[O + 56]), "+f"(d[O + 57]), "+f"(d[O + 58]), "+f"(d[O + 59]), "+f"(d[O + 60]), "+f"(d[O + 61]), "+f"(d[O + 62]), "+f"(d[O + 63])
        : "l"(da), "l"(db), "r"(scale_d), "n"(TA), "n"(TB));
}
template <int TA, int TB, int O = 0, int NR> __device__ __forceinline__ void wgmma_ss_bf16_n64(float (&d)[NR], uint64_t da, uint64_t db, int scale_d) {
    asm volatile("{.reg .pred p; setp.ne.b32 p, %34, 0;\n"
        "wgmma.mma_async.sync.aligned.m64n64k16.f32.bf16.bf16 {%0,%1,%2,%3,%4,%5,%6,%7,%8,%9,%10,%11,%12,%13,%14,%15,%16,%17,%18,%19,%20,%21,%22,%23,%24,%25,%26,%27,%28,%29,%30,%31}, %32, %33, p, 1, 1, %35, %36;}"
        : "+f"(d[O + 0]), "+f"(d[O + 1]), "+f"(d[O + 2]), "+f"(d[O + 3]), "+f"(d[O + 4]), "+f"(d[O + 5]), "+f"(d[O + 6]), "+f"(d[O + 7]), "+f"(d[O + 8]), "+f"(d[O + 9]), "+f"(d[O + 10]), "+f"(d[O + 11]), "+f"(d[O + 12]), "+f"(d[O + 13]), "+f"(d[O + 14]), "+f"(d[O + 15]), "+f"(d[O + 16]), "+f"(d[O + 17]), "+f"(d[O + 18]), "+f"(d[O + 19]), "+f"(d[O + 20]), "+f"(d[O + 21]), "+f"(d[O + 22]), "+f"(d[O + 23]), "+f"(d[O + 24]), "+f"(d[O + 25]), "+f"(d[O + 26]), "+f"(d[O + 27]), "+f"(d[O + 28]), "+f"(d[O + 29]), "+f"(d[O + 30]), "+f"(d[O + 31])
        : "l"(da), "l"(db), "r"(scale_d), "n"(TA), "n"(TB));
}
template <int TA, int TB, int O = 0, int NR> __device__ __forceinline__ void wgmma_ss_f16_n64(float (&d)[NR], uint64_t da, uint64_t db, int scale_d) {
    asm volatile("{.reg .pred p; setp.ne.b32 p, %34, 0;\n"
        "wgmma.mma_async.sync.aligned.m64n64k16.f32.f16.f16 {%0,%1,%2,%3,%4,%5,%6,%7,%8,%9,%10,%11,%12,%13,%14,%15,%16,%17,%18,%19,%20,%21,%22,%23,%24,%25,%26,%27,%28,%29,%30,%31}, %32, %33, p, 1, 1, %35, %36;}"
        : "+f"(d[O + 0]), "+f"(d[O + 1]), "+f"(d[O + 2]), "+f"(d[O + 3]), "+f"(d[O + 4]), "+f"(d[O + 5]), "+f"(d[O + 6]), "+f"(d[O + 7]), "+f"(d[O + 8]), "+f"(d[O + 9]), "+f"(d[O + 10]), "+f"(d[O + 11]), "+f"(d[O + 12]), "+f"(d[O + 13]), "+f"(d[O + 14]), "+f"(d[O + 15]), "+f"(d[O + 16]), "+f"(d[O + 17]), "+f"(d[O + 18]), "+f"(d[O + 19]), "+f"(d[O + 20]), "+f"(d[O + 21]), "+f"(d[O + 22]), "+f"(d[O + 23]), "+f"(d[O + 24]), "+f"(d[O + 25]), "+f"(d[O + 26]), "+f"(d[O + 27]), "+f"(d[O + 28]), "+f"(d[O + 29]), "+f"(d[O + 30]), "+f"(d[O + 31])
        : "l"(da), "l"(db), "r"(scale_d), "n"(TA), "n"(TB));
}

constexpr uint64_t DHI = (uint64_t)0x40000040u << 32;
__device__ __forceinline__ uint64_t dsc(uint32_t lo) { return DHI | lo; }
constexpr uint32_t LBO8K = (8192u >> 4) << 16, LBO1 = 1u << 16;

__device__ __forceinline__ int pos2b(int p) { return (p & 32) | ((p & 6) << 2) | ((p & 24) >> 2) | (p & 1); }

__device__ __forceinline__ int ygrp(int i) { return (i >> 5) | ((i & 31) << 2); }
__device__ __forceinline__ void w_records(uint32_t sm, int rec0, int nrec, int c, int v0, bool on, int lane) {
#pragma unroll 1
    for (int n = 0; n < nrec; n++) {
        const int wo = ((rec0 + n) >> 2) & 7, vv = v0 + (wo >> 1);
        const uint32_t img = sm + n * WIMG;
        uint32_t v[16];
        mbar_wait(sm + OFF_BAR + 8 * (BAR_RF + n), 0);
#pragma unroll
        for (int i = 0; i < 16; i++) v[i] = lds32(img + c * 8448 + i * 528 + vv * 4);
        bar_sync(3, 288);
#pragma unroll
        for (int j = 0; j < 2; j++) {
            const int k = 2 * vv - wo + j; const uint32_t sel = j ? 0x7632 : 0x5410;
            const uint32_t a = img + (k >> 1) * 128 + (((4 * (k & 1) + 2 * c) ^ ((k >> 1) & 7)) << 4);
            if (on && (unsigned)k <= 256u) {
#pragma unroll
                for (int q = 0; q < 2; q++)
                    sts128(a ^ (q << 4), __byte_perm(v[q], v[2 + q], sel), __byte_perm(v[4 + q], v[6 + q], sel), __byte_perm(v[8 + q], v[10 + q], sel), __byte_perm(v[12 + q], v[14 + q], sel));
            }
        }
        __syncwarp();
        mbar_arrive_p(sm + OFF_BAR + 8 * (BAR_RD + n), lane == 0);
    }
}
template <int F0, int NV, int N>
__device__ __forceinline__ void xsend(float (&acc)[N], uint32_t dst, uint32_t bar) {
#pragma unroll
    for (int i = 0; i < NV; i++)
        st_async4(dst + i * 512, pk_b(acc[F0 + 8 * i], acc[F0 + 8 * i + 1]), pk_b(acc[F0 + 8 * i + 2], acc[F0 + 8 * i + 3]),
                  pk_b(acc[F0 + 8 * i + 4], acc[F0 + 8 * i + 5]), pk_b(acc[F0 + 8 * i + 6], acc[F0 + 8 * i + 7]), bar);
}
template <int N0, int NT>
__device__ __forceinline__ void epi1(const float (&acc)[64], const uint32_t (&p)[16], uint32_t xw, int lane, __nv_bfloat16* up) {
    uint32_t r[8] = {};
#pragma unroll
    for (int j = 0; j < NT; j++) {
        float v[2] = {acc[4 * (N0 + j)] + bf_lo(p[N0 + j]), acc[4 * (N0 + j) + 1] + bf_hi(p[N0 + j])};
#pragma unroll
        for (int e = 0; e < 2; e++) {
            const float q = v[e], z = q * fmaf(q * q, 64.f * 0.035677408136300125f, 4.f * 0.7978845608028654f);
            v[e] = fmaf(q, tanh_fast(z), q);
        }
        r[j] = pk_b(v[0], v[1]);
    }
#pragma unroll
    for (int i = 0; i < 2; i++) stsm4(xw + (lane & 7) * 128 + (((4 * i + (lane >> 3)) ^ (lane & 7)) << 4), r[4 * i], r[4 * i + 1], r[4 * i + 2], r[4 * i + 3]);
    __syncwarp();
#pragma unroll
    for (int i = 0; i < 2; i++) {
        const int rr = 4 * i + (lane >> 3), c = lane & 7;
        const uint4 o = lds128(xw + rr * 128 + ((c ^ rr) << 4));
        if (c < NT) asm volatile("st.global.v4.u32 [%0], {%1,%2,%3,%4};" :: "l"(up + rr * 1792 + c * 8), "r"(o.x), "r"(o.y), "r"(o.z), "r"(o.w) : "memory");
    }
}

template <int S, int BF, int BE, int OFF>
struct Ring {
    uint32_t s, ph, bar0, base;
    __device__ __forceinline__ Ring(uint32_t sm, int item) : s(item % S), ph(((item / S) & 1) ^ 1), bar0(sm + OFF_BAR), base(sm + OFF) {}
    __device__ __forceinline__ uint32_t full() const { return bar0 + 8 * BF + 8 * s; }
    __device__ __forceinline__ uint32_t dst() const { return base + s * SLOT; }
    __device__ __forceinline__ void acquire(uint32_t bytes) { mbar_wait(bar0 + 8 * BE + 8 * s, ph); mbar_expect(full(), bytes); }
    __device__ __forceinline__ void next() { if (++s == S) { s = 0; ph ^= 1; } }
};

template <int NIT, int IA, int IB, int KA, class MMA>
__device__ __forceinline__ void mainloop(uint32_t bar0, uint32_t alo, uint32_t blo, bool leader, int wg, int lag, MMA mma) {
    uint32_t sa = IA % SA, pa = (IA / SA) & 1, sb = IB % SB, pb = (IB / SB) & 1, ra = 0, rb = 0;
#pragma unroll 1
    for (int it = 0; it < NIT; it++) {
        mbar_wait(bar0 + 8 * (BAR_FB + sb), pb);
        mbar_wait(bar0 + 8 * (BAR_FA + sa), pa);
        if (lag) { if (wg) { if (it == NIT - lag) bar_sync(12, 256); } else if (it == NIT - 1) bar_arrive(12, 256); }
        wg_fence();
#pragma unroll
        for (int k = 0; k < 4; k++) mma(dsc(alo + sa * 1024 + k * KA), dsc(blo + sb * 1024 + k * 128));
        wg_commit();
        wg_wait<1>();
        mbar_arrive_p(bar0 + 8 * (BAR_EA + ra), leader && it > 0);
        mbar_arrive_p(bar0 + 8 * (BAR_EB + rb), leader && it > 0);
        ra = sa; rb = sb;
        if (++sa == SA) { sa = 0; pa ^= 1; }
        if (++sb == SB) { sb = 0; pb ^= 1; }
    }
}

__global__ void __cluster_dims__(2, 1, 1) __launch_bounds__(384, 1)
fused_kernel(const __nv_bfloat16* __restrict__ x, Scratch* sc_, TUNE_PARAM const __nv_bfloat16* __restrict__ w1,
             const __nv_bfloat16* __restrict__ b1,
             const __nv_bfloat16* __restrict__ b2, const __grid_constant__ Maps M) {
    const uint32_t t0 = clk();
    Scratch& S_ = *sc_;
    extern __shared__ __align__(1024) uint8_t smem_raw[];
    uint32_t smid, rank;
    asm volatile("mov.u32 %0, %%smid;" : "=r"(smid));
    const int lane = threadIdx.x & 31;
    const bool spare = (smid >> 2) == 30;
    const int cid = spare ? smid & 3 : smid - (smid >= 124 ? 4 : 0);
    const uint32_t sm = (uint32_t)__cvta_generic_to_shared(smem_raw);
    uint2 xr[2][4];
    float sc[2] = {0.f, 0.f}, of[2] = {0.f, 0.f};
    if (threadIdx.x < 256 && !spare) {
        const int xoff = (64 * (16 * (cid >> 6) + 2 * (threadIdx.x >> 5)) + pos2b(cid & 63)) * 512 + 32 * (lane & 3) + 4 * (lane & 4) + 4 * (lane >> 3);
#pragma unroll
        for (int c = 0; c < 4; c++)
            asm volatile("ld.global.nc.v2.u32 {%0,%1}, [%2];" : "=r"(xr[0][c].x), "=r"(xr[0][c].y) : "l"(x + xoff + 128 * c));
        if (threadIdx.x == 0) STAMP(29);
        const int g = lane >> 2;
        wait_until(t0, T_XB);
        if (lane < 8) asm volatile("prefetch.global.L2 [%0];" :: "l"(x + (xoff & ~511) + 32768 + 64 * lane));
        {
            const int wp = threadIdx.x >> 5, q = (wp >> 1) & 1, nu = wp & 1, mu = 15 - 2 * g - nu;
            const bool wg = wp >= 4;
            const int R = wg ? 32 * (2 * mu + 1) : 64 * (2 * (8 * nu + g) + q), S = wg ? (((mu ^ q) & 1) ? -256 : 256) : 0, S2 = wg ? 512 : -512;
            const float amp = wg ? 0.70710678118654752f : 1.f;
            uint32_t o[4];
#pragma unroll
            for (int i = 0; i < 4; i++) {
                const int A = (4 * (lane & 3) + 2 * (i & 1)) * R + S + (i >> 1) * S2;
                o[i] = pk_h(amp * cos2048(A), amp * cos2048(A + R));
            }
            sts128(sm + OFF_FR + 512 + threadIdx.x * 16, o[0], o[1], o[2], o[3]);
        }
        if (threadIdx.x == 0) STAMP(58);
        __nv_bfloat16* hp = S_.h + (xoff ^ ((cid >> 3) & 8)) - 32768;
        uint2 xi[4] = {};
        if (!DRY) {
            hp += 32768;
            wait_until(t0, 8);
#pragma unroll
            for (int c = 0; c < 4; c++) xi[c] = xr[0][c];
        }
#pragma unroll
        for (int c = 0; c < 4; c++) xr[1][c] = make_uint2(0, 0);
#pragma unroll 1
        for (int pass = DRY ? 0 : 1;; pass++) {
            const uint32_t ones = 0x3f803f80u;
            float S[4] = {0.f, 0.f, 0.f, 0.f}, S2[4] = {0.f, 0.f, 0.f, 0.f};
            mma_b(S, xi[0].x, ones, xi[0].y, ones, xi[0].x, xi[0].y);
            mma_b(S2, xi[1].x, ones, xi[1].y, ones, xi[1].x, xi[1].y);
            mma_b(S, xi[2].x, ones, xi[2].y, ones, xi[2].x, xi[2].y);
            mma_b(S2, xi[3].x, ones, xi[3].y, ones, xi[3].x, xi[3].y);
            float s1 = (S[2] + S[3]) + (S2[2] + S2[3]);
            float s2 = __shfl_sync(0xffffffffu, (g & 1) ? S[1] + S2[1] : S[0] + S2[0], (lane & 28) | (g >> 1));
            if (threadIdx.x == 0) STAMP(pass == 2 ? 42 : 1);
            {
                const uint32_t go = pass == 1 && __float_as_uint(s2) != 0xffc12345u;
#pragma unroll
                for (int c = 0; c < 4; c++)
                    asm volatile("{.reg .pred p; setp.ne.u32 p, %3, 0; @p ld.global.nc.v2.u32 {%0,%1}, [%2];}" : "+r"(xr[1][c].x), "+r"(xr[1][c].y) : "l"(x + xoff + 32768 + 128 * c), "r"(go));
            }
#pragma unroll
            for (int o = 0; o < 3; o++) {
                if (o < 2) s1 += __shfl_xor_sync(0xffffffffu, s1, 1 << o);
                s2 += __shfl_xor_sync(0xffffffffu, s2, 4 << o);
            }
            const float m = s1 * (1.f / 512.f), var = fmaxf(fmaf(-m, m, s2 * (1.f / 512.f)), 0.f);
            const float r1 = rsqrt_fast(var + 1e-5f), R = 0.25f * rsqrt_fast(fmaf(var + 1e-5f, 1e-5f, var));
            const uint32_t Rh = pk_b(R, R); const float rl = R - bf_lo(Rh); const uint32_t Rl = pk_b(rl, rl), Ob = pk_b(-m * R, -m * R);
            sc[0] = sc[1]; of[0] = of[1];
            sc[1] = 64.f * r1; of[1] = -m * sc[1];
#pragma unroll
            for (int c = 0; c < 4; c++)
                asm volatile("{.reg .pred p; setp.ne.u32 p, %3, 0; @p st.global.v2.u32 [%0], {%1,%2};}" :: "l"(hp + 128 * c),
                             "r"(fma_b2(xi[c].x, Rh, fma_b2(xi[c].x, Rl, Ob))), "r"(fma_b2(xi[c].y, Rh, fma_b2(xi[c].y, Rl, Ob))), "r"(pass) : "memory");
            hp += 32768;
            if (threadIdx.x == 0) STAMP(pass == 2 ? 43 : pass ? 2 : 57);
            if (pass == 0) {
                wait_until(t0, 8);
#pragma unroll
                for (int c = 0; c < 4; c++) xi[c] = xr[0][c];
            } else {
                bar_arrive(pass == 1 ? 2 : 9, 288);
                if (pass == 2) break;
                wait_until(t0, 8);
#pragma unroll
                for (int c = 0; c < 4; c++) xi[c] = xr[1][c];
            }
        }
    }
    constexpr uint32_t smd = 1024 >> 4;
    if ((sm & 0xFFFFFF) != 1024) __trap();
    const uint32_t bar0 = sm + OFF_BAR;
    if ((threadIdx.x >> 5) == 10) {
        if (elect()) {
#pragma unroll
            for (int i = 0; i < NBAR; i++) mbar_init(bar0 + 8 * i, i == BAR_FR ? 12 : ((i >= BAR_EA && i < BAR_FB) || (i >= BAR_EB && i < BAR_XC) || i == BAR_WD) ? 2 : 1);
            asm volatile("fence.mbarrier_init.release.cluster;" ::: "memory");
        }
        __syncwarp();
        bar_arrive(1, 288);
    }
    const int warp = __reduce_max_sync(0xffffffffu, threadIdx.x >> 5);
    asm volatile("mov.u32 %0, %%cluster_ctarank;" : "=r"(rank));
    const int tpc = smid >> 1;
    int gpc, idx;
    if (tpc < 32) { gpc = tpc & 7; idx = tpc >> 3; }
    else if (tpc < 60) { gpc = 1 + (tpc - 32) % 7; idx = 4 + (tpc - 32) / 7; }
    else { gpc = 0; idx = tpc - 58; }
    const int dblk = idx & 3, nblk = gpc * 2 + (idx >> 2);
    const bool nog1 = gpc == 0;
    const int f0 = (nblk - 2) * 128;
    const int wj = ((0x76154032 >> (4 * idx)) & 7) * 2 + rank, nx = 48 - 4 * NSP;
    const int rec0 = spare ? 128 - (cid + 1) * NSP : 5 * wj + min(wj, nx), nrec = spare ? NSP : 5 + (wj < nx);
    const int s_own = nblk * 128 + rank * 64, s_for = nblk * 128 + (rank ^ 1) * 64;
    unsigned* cnt = S_.cnt;

    if (warp < 8) {
        const int wg = warp >> 2, w = warp & 3, g = lane >> 2, t = lane & 3;
        const int tid = threadIdx.x;
        const bool leader = (tid & 127) == 0;
        uint32_t b1r[16], b2r[8];
        asm volatile("setmaxnreg.inc.sync.aligned.u32 216;");
        bar_sync(1, 288);
        mbar_arrive_p(bar0 + 8 * BAR_FR, lane == 0);
        const uint32_t xw = sm + OFF_X + warp * 2048;
        float acc1[64];
        if (!spare) {
            uint4 fr[13];
            mbar_wait(bar0 + 8 * BAR_FR, 0);
#pragma unroll
            for (int Q = 0; Q < 13; Q++) fr[Q] = lds128(sm + OFF_FR + Q * 512 + lane * 16);
            const uint32_t gm = g == 0 ? 0u : 0xffffffffu;
            float Dq[2][2][2][4];
            uint32_t ui[2][2][2];
#pragma unroll
            for (int r = 0; r < 2; r++) {
                float Ur[2][4], Ui[2][4], v[16];
#pragma unroll
                for (int c = 0; c < 4; c++) { v[4 * c] = bf_lo(xr[r][c].x); v[4 * c + 1] = bf_hi(xr[r][c].x); v[4 * c + 2] = bf_lo(xr[r][c].y); v[4 * c + 3] = bf_hi(xr[r][c].y); }
#pragma unroll
                for (int e = 0; e < 4; e++) {
                    float T[4] = {0.f, 0.f, 0.f, 0.f};
                    mma_h(T, fr[0].x, fr[0].y, fr[0].z, fr[0].w,
                          pk_h(fmaf(v[e], sc[r], of[r]), fmaf(v[4 + e], sc[r], of[r])),
                          pk_h(fmaf(v[8 + e], sc[r], of[r]), fmaf(v[12 + e], sc[r], of[r])));
                    const float c0 = __uint_as_float(fr[9 + e].x), n0 = __uint_as_float(fr[9 + e].y), c1 = __uint_as_float(fr[9 + e].z), n1 = __uint_as_float(fr[9 + e].w);
                    const float pr = fmaf(T[0], c0, -T[2] * n0), pi = fmaf(T[0], n0, T[2] * c0);
                    Ur[0][e] = fmaf(T[1], c1, fmaf(-T[3], n1, pr)); Ui[0][e] = fmaf(T[1], n1, fmaf(T[3], c1, pi));
                    Ur[1][e] = fmaf(2.f, pr, -Ur[0][e]); Ui[1][e] = fmaf(2.f, pi, -Ui[0][e]);
                }
#pragma unroll
                for (int q = 0; q < 2; q++) {
                    const uint32_t a0 = pk_h(Ur[q][0], Ur[q][1]), a2 = pk_h(Ur[q][2], Ur[q][3]);
                    ui[r][q][0] = pk_h(Ui[q][0], Ui[q][1]); ui[r][q][1] = pk_h(Ui[q][2], Ui[q][3]);
                    const uint32_t a1 = ui[r][q][0] & gm, a3 = ui[r][q][1] & gm;
#pragma unroll
                    for (int nu = 0; nu < 2; nu++) {
                        float (&d)[4] = Dq[r][q][nu];
                        d[0] = d[1] = d[2] = d[3] = 0.f;
                        const uint4 B = fr[1 + 2 * q + nu];
                        mma_h(d, a0, a1, a2, a3, B.x, B.y);
                        mma_h(d, a1, a0 ^ 0x80008000u, a3, a2 ^ 0x80008000u, B.z, B.w);
                    }
                }
            }
            float Ex[2][2][4];
#pragma unroll
            for (int nu = 0; nu < 2; nu++)
#pragma unroll
                for (int c = 0; c < 2; c++) {
                    float (&d)[4] = Ex[nu][c];
                    d[0] = d[1] = d[2] = d[3] = 0.f;
#pragma unroll
                    for (int q = 0; q < 2; q++) {
                        const uint4 B = fr[5 + 2 * q + nu];
                        mma_h(d, ui[0][q][0], ui[1][q][0], ui[0][q][1], ui[1][q][1], c ? B.z : B.x, c ? B.w : B.y);
                    }
                }
#pragma unroll
            for (int nu = 0; nu < 2; nu++) {
                const int kl = nu ? (g == 0 ? 8 : 16 - g) : g, tt = nu ? 3 - t : t;
                const int r0 = tt | ((kl >> 1) << 2);
                const uint32_t ya = sm + OFF_X + r0 * 128 + (((4 * (kl & 1) + (warp >> 1)) ^ (r0 & 7)) << 4) + (warp & 1) * 8;
#pragma unroll
                for (int q = 0; q < 2; q++)
#pragma unroll
                    for (int e = 0; e < 2; e++) {
                        uint32_t re = pk_h(Dq[0][q][nu][e], Dq[1][q][nu][e]);
                        uint32_t im = nu ? pk_h(-Dq[0][q][1][2 + e], -Dq[1][q][1][2 + e]) : pk_h(Dq[0][q][0][2 + e], Dq[1][q][0][2 + e]);
                        if (nu) {
                            if (q == 0 && e == 0 && lane == 0) sts64(sm + OFF_X + 16384 + warp * 8, re, 0u);
                            if (g == 0) { re = pk_h(Ex[q][0][e], Ex[q][0][2 + e]); im = pk_h(Ex[q][1][e], Ex[q][1][2 + e]); }
                        }
                        sts64(ya + (nu ? 3 - (2 * e + q) : 2 * e + q) * 4096, re, im);
                    }
            }
            bar_arrive(4, 288);
            {
                const uint32_t* pb1 = (const uint32_t*)(b1 + max(f0, 0)) + t;
                const uint32_t* pb2 = (const uint32_t*)(b2 + s_own) + t;
#pragma unroll
                for (int n = 0; n < 16; n++) asm volatile("ld.global.u32 %0, [%1];" : "=r"(b1r[n]) : "l"(pb1 + 4 * n) : "memory");
#pragma unroll
                for (int n = 0; n < 8; n++) asm volatile("ld.global.u32 %0, [%1];" : "=r"(b2r[n]) : "l"(pb2 + 4 * n) : "memory");
            }
            if (tid == 0) STAMP(3);
        }
        if (nog1 && !spare) {
#pragma unroll 1
            for (int wd = wj * 256 + tid; wd < 8192; wd += 4096) {
                const int mat = wd >> 11, r = (wd >> 5) & 63, c = ((((wd >> 2) & 7) ^ (r & 7)) << 3) | ((wd & 3) << 1);
                int A, dA;
                if (mat == 0) { dA = 64 * (8 * (r >> 4) + (r & 7)); A = ((c >> 2) << 1) * dA + 512 * (((r >> 3) & 1) - ((c >> 1) & 1)); }
                else if (mat == 1) { dA = 32 * (2 * (r & 31) + (r >> 5)); A = pos2b(c & 31) * dA - 512 * (c >> 5); }
                else if (mat == 2) { dA = 64 * pos2b(r & 31); A = (2 * (c & 31) + (r >> 5)) * (dA >> 1) + 512 * (c >> 5); }
                else { dA = 64 * (r & 31); A = (8 * (c >> 4) + (c & 7)) * dA + 512 * (((c >> 3) & 1) - (r >> 5)); }
                const float v0 = cos2048(A), v1 = cos2048(A + dA);
                ((uint32_t*)S_.T)[wd] = mat < 2 ? pk_h(v0, v1) : pk_b(v0, v1);
            }
            bar_arrive(12, 288);
        }
        if (nog1) { mbar_wait(bar0 + 8 * BAR_FR, 0); w_records(sm, rec0, nrec, wg, tid & 127, true, lane); }
        if (spare) {
            mbar_wait(bar0 + 8 * BAR_YR, 0);
#pragma unroll 2
            for (int wd = cid * 256 + tid; wd < 65536; wd += 1024) {
                const int d = (wd >> 7) & 255, k = 2 * (wd & 127) + (wd >> 15);
                const float sc_v = k ? 1.220703125e-4f : 6.103515625e-5f;
                ((uint32_t*)S_.C)[wd] = pk_b(sc_v * cos2048(4 * k * d), sc_v * cos2048(k ? 4 * k * d + 512 : 1024 * d));
            }
            bar_arrive(4, 288);
            if (cid != 0 || wg != 0) return;
        }
        float twc[16], tws[16];
        {
            const int j1 = 8 * w + g;
            const float cs_ = cos2048(j1), ss_ = cos2048(j1 + 512);
#pragma unroll
            for (int h = 0; h < 2; h++) {
                float c = cos2048(j1 * (8 * t + 32 * h)) * 0.015625f, s = cos2048(j1 * (8 * t + 32 * h) + 512) * 0.015625f;
#pragma unroll
                for (int i = 0; i < 8; i++) {
                    twc[8 * h + i] = c; tws[8 * h + i] = s;
                    const float c2 = fmaf(c, cs_, -s * ss_); s = fmaf(c, ss_, s * cs_); c = c2;
                }
            }
        }
        pin(twc); pin(tws);
        uint32_t peer; asm("mapa.shared::cluster.u32 %0, %1, %2;" : "=r"(peer) : "r"(sm), "r"(rank ^ 1));
        if (!nog1) {
#pragma unroll
            for (int n = 0; n < 16; n++) { acc1[4 * n] = 0.25f * bf_lo(b1r[n]); acc1[4 * n + 1] = 0.25f * bf_hi(b1r[n]); acc1[4 * n + 2] = acc1[4 * n + 3] = 0.f; }
            pin(acc1);
            if (lane == 0) mbar_expect(bar0 + 8 * (BAR_XC + warp), 2048);
            const uint32_t alo = (smd + ((OFF_A + wg * 8192) >> 4)) | LBO8K, blo = (smd + (OFF_B >> 4)) | LBO8K;
            mainloop<16, 0, 0, 128>(bar0, alo, blo, leader, wg, LAG1, [&](uint64_t a, uint64_t b) { wgmma_ss_bf16_n128<1, 1>(acc1, a, b, 1); });
            mbar_wait(bar0 + 8 * BAR_WD, 0);
            const uint32_t xdst = peer + OFF_X + XB + warp * 2048 + lane * 16, boff = OFF_BAR + 8 * (BAR_XC + warp);
            wg_wait<0>();
            pin(acc1);
            if (leader) STAMP(wg ? 52 : 5);
#pragma unroll
            for (int i = 0; i < 4; i++)
                st_async4(xdst + i * 512, pk_b(acc1[16 * i + 2], acc1[16 * i + 3]), pk_b(acc1[16 * i + 6], acc1[16 * i + 7]),
                          pk_b(acc1[16 * i + 10], acc1[16 * i + 11]), pk_b(acc1[16 * i + 14], acc1[16 * i + 15]), peer + boff);
            mbar_arrive_p(bar0 + 8 * (BAR_EA + 15 % SA), leader);
            mbar_arrive_p(bar0 + 8 * (BAR_EB + 15 % SB), leader);
        }
        uint32_t a[2][8];
        float T[32];
        const uint32_t c0 = smd + ((OFF_A + (IA_C0 % SA) * SLOT) >> 4);
        {
            const uint32_t yb = smd + ((OFF_A + (IA_Y % SA) * SLOT) >> 4) + wg * 4;
            mbar_wait(bar0 + 8 * (BAR_FA + IA_Y % SA), (IA_Y / SA) & 1);
            mbar_wait(bar0 + 8 * (BAR_FA + IA_C0 % SA), (IA_C0 / SA) & 1);
            if (tid == 0) STAMP(30);
            wg_fence();
#pragma unroll
            for (int k = 0; k < 4; k++) wgmma_ss_f16_n64<0, 0>(T, dsc((c0 + k * 2) | LBO1), dsc((yb + (k >> 1) * 512 + (k & 1) * 2) | LBO1), k);
            wg_commit();
            wg_wait<0>();
            pin(T);
            mbar_arrive_p(bar0 + 8 * (BAR_EA + IA_Y % SA), leader);
#pragma unroll
            for (int n = 0; n < 4; n++) {
                float ur[2][2], uim[2][2];
#pragma unroll
                for (int e = 0; e < 2; e++) {
                    const int i = 2 * n + e;
                    const float pr = fmaf(T[4 * n + e], twc[i], -T[4 * n + 2 + e] * tws[i]), pi = fmaf(T[4 * n + e], tws[i], T[4 * n + 2 + e] * twc[i]);
                    ur[0][e] = fmaf(T[16 + 4 * n + e], twc[8 + i], fmaf(-T[18 + 4 * n + e], tws[8 + i], pr));
                    uim[0][e] = fmaf(T[16 + 4 * n + e], tws[8 + i], fmaf(T[18 + 4 * n + e], twc[8 + i], pi));
                    ur[1][e] = fmaf(2.f, pr, -ur[0][e]); uim[1][e] = fmaf(2.f, pi, -uim[0][e]);
                }
#pragma unroll
                for (int q = 0; q < 2; q++) { a[q][2 * n] = pk_h(ur[q][0], ur[q][1]); a[q][2 * n + 1] = pk_h(uim[q][0], uim[q][1]); }
            }
#pragma unroll
            for (int i = 0; i < 16; i++) asm volatile("" : "+r"(a[i >> 3][i & 7]) :: "memory");
            if (tid == 0) STAMP(33);
        }
        if (!nog1) {
            __nv_bfloat16* up = S_.u + (dblk * 64 + wg * 256 + w * 16 + rank * 8) * 1792 + f0;
            mbar_wait(bar0 + 8 * (BAR_XC + warp), 0);
            if (leader) STAMP(wg ? 55 : 20);
            uint32_t pp[16];
#pragma unroll
            for (int i = 0; i < 4; i++) { const uint4 v = lds128(xw + XB + i * 512 + lane * 16); pp[4 * i] = v.x; pp[4 * i + 1] = v.y; pp[4 * i + 2] = v.z; pp[4 * i + 3] = v.w; }
            epi1<0, 8>(acc1, pp, xw, lane, up);
            bar_arrive(2, 288);
            if (leader) STAMP(wg ? 51 : 39);
            mbar_wait(bar0 + 8 * (BAR_XC + warp), 0);
            epi1<8, 8>(acc1, pp, xw + 1024, lane, up + 64);
            __syncwarp();
            bar_arrive(5, 288);
            if (leader) STAMP(wg ? 53 : 6);
        }
        if (lane == 0) mbar_expect(bar0 + 8 * (BAR_XC + warp), 2048);
        {
            const uint32_t c1 = smd + ((OFF_A + (IA_C1 % SA) * SLOT) >> 4);
            float X[2][16];
            uint32_t an[2][4];
#pragma unroll
            for (int q = 0; q < 2; q++)
#pragma unroll
                for (int n = 0; n < 4; n++) an[q][n] = a[q][2 * n] ^ 0x80008000u;
            wg_fence();
#pragma unroll
            for (int k = 0; k < 2; k++) {
#pragma unroll
                for (int q = 0; q < 2; q++)
                    wgmma_rs_f16_n32<0>(X[q], a[q][4 * k], a[q][4 * k + 1], a[q][4 * k + 2], a[q][4 * k + 3], dsc((c0 + 512 + q * 256 + k * 2) | LBO1), k);
#pragma unroll
                for (int q = 0; q < 2; q++)
                    wgmma_rs_f16_n32<0>(X[q], a[q][4 * k + 1], an[q][2 * k], a[q][4 * k + 3], an[q][2 * k + 1], dsc((c0 + 512 + q * 256 + 4 + k * 2) | LBO1), 1);
            }
            wg_commit();
            mbar_wait(bar0 + 8 * (BAR_FA + IA_W % SA), (IA_W / SA) & 1);
            uint4 wq[4];
#pragma unroll
            for (int i = 0; i < 4; i++) wq[i] = lds128(sm + OFF_A + (IA_W % SA) * SLOT + (tid & 127) * 128 + (((4 * wg + i) ^ (tid & 7)) << 4));
            mbar_wait(bar0 + 8 * (BAR_FA + IA_C1 % SA), (IA_C1 / SA) & 1);
            wg_wait<0>();
            pin(X[0]); pin(X[1]);
            mbar_arrive_p(bar0 + 8 * (BAR_EA + IA_C0 % SA), leader);
            if (tid == 0) STAMP(34);
#pragma unroll
            for (int q = 0; q < 2; q++) {
                const uint32_t wre[4] = {wq[q].x, wq[q].y, wq[q].z, wq[q].w}, wim[4] = {wq[2 + q].x, wq[2 + q].y, wq[2 + q].z, wq[2 + q].w};
#pragma unroll
                for (int n = 0; n < 4; n++) {
                    const float r0 = bf_lo(wre[n]), r1 = bf_hi(wre[n]), i0 = bf_lo(wim[n]), i1 = bf_hi(wim[n]);
                    a[q][2 * n] = pk_b(fmaf(X[q][4 * n], r0, -X[q][4 * n + 2] * i0), fmaf(X[q][4 * n + 1], r1, -X[q][4 * n + 3] * i1));
                    a[q][2 * n + 1] = pk_b(fmaf(X[q][4 * n], i0, X[q][4 * n + 2] * r0), fmaf(X[q][4 * n + 1], i1, X[q][4 * n + 3] * r1));
                    an[q][n] = a[q][2 * n] ^ 0x80008000u;
                }
            }
            wg_fence();
#pragma unroll
            for (int k = 0; k < 2; k++) {
#pragma unroll
                for (int q = 0; q < 2; q++)
                    wgmma_rs_bf16_n32<0>(X[q], a[q][4 * k], a[q][4 * k + 1], a[q][4 * k + 2], a[q][4 * k + 3], dsc((c1 + q * 256 + k * 2) | LBO1), k);
#pragma unroll
                for (int q = 0; q < 2; q++)
                    wgmma_rs_bf16_n32<0>(X[q], a[q][4 * k + 1], an[q][2 * k], a[q][4 * k + 3], an[q][2 * k + 1], dsc((c1 + q * 256 + 4 + k * 2) | LBO1), 1);
            }
            wg_commit();
            wg_wait<0>();
            pin(X[0]); pin(X[1]);
            uint32_t tp[16];
#pragma unroll
            for (int h = 0; h < 2; h++)
#pragma unroll
                for (int n = 0; n < 4; n++) {
                    float re[2], im[2];
#pragma unroll
                    for (int e = 0; e < 2; e++) {
                        const int i = 8 * h + 2 * n + e;
                        const float vr = h ? X[0][4 * n + e] - X[1][4 * n + e] : X[0][4 * n + e] + X[1][4 * n + e];
                        const float vi = h ? X[0][4 * n + 2 + e] - X[1][4 * n + 2 + e] : X[0][4 * n + 2 + e] + X[1][4 * n + 2 + e];
                        re[e] = fmaf(vr, twc[i], vi * tws[i]); im[e] = fmaf(vi, twc[i], -vr * tws[i]);
                    }
                    tp[8 * h + 2 * n] = pk_b(re[0], re[1]); tp[8 * h + 2 * n + 1] = pk_b(im[0], im[1]);
                }
            const int row = (lane & 7) + (lane & 8), hi = lane >> 4;
#pragma unroll
            for (int i = 0; i < 4; i++) stsm4(xw + row * 128 + (((2 * i + hi) ^ (lane & 7)) << 4), tp[4 * i], tp[4 * i + 1], tp[4 * i + 2], tp[4 * i + 3]);
            asm volatile("fence.proxy.async.shared::cta;" ::: "memory");
            bar_sync(6 + wg, 128);
            mbar_arrive_p(bar0 + 8 * (BAR_EA + IA_W % SA), leader);
            wg_fence();
            const uint32_t tbd = smd + ((OFF_X + wg * 8192) >> 4);
#pragma unroll
            for (int k = 0; k < 4; k++) wgmma_ss_bf16_n64<0, 1>(T, dsc((c1 + 512 + k * 2) | LBO1), dsc((tbd + k * 128) | LBO8K), k);
            wg_commit();
            wg_wait<0>();
            pin(T);
            mbar_arrive_p(bar0 + 8 * (BAR_EA + IA_C1 % SA), leader);
#pragma unroll
            for (int r = 0; r < 2; r++)
#pragma unroll
                for (int h = 0; h < 2; h++)
                    sts128(xw + XB + (g + 8 * r) * 128 + h * 64 + t * 16, pk_b(T[16 * h + 2 * r], T[16 * h + 2 * r + 1]), pk_b(T[16 * h + 4 + 2 * r], T[16 * h + 5 + 2 * r]),
                           pk_b(T[16 * h + 8 + 2 * r], T[16 * h + 9 + 2 * r]), pk_b(T[16 * h + 12 + 2 * r], T[16 * h + 13 + 2 * r]));
            if (spare) { bar_arrive(8, 160); return; }
            bar_arrive(8, 288);
            if (leader) STAMP(wg ? 54 : 7);
        }
        float acc[64];
#pragma unroll
        for (int n = 0; n < 8; n++) {
            acc[4 * n] = acc[4 * n + 2] = 0.5f * bf_lo(b2r[n]); acc[4 * n + 1] = acc[4 * n + 3] = 0.5f * bf_hi(b2r[n]);
            acc[32 + 4 * n] = acc[33 + 4 * n] = acc[34 + 4 * n] = acc[35 + 4 * n] = 0.f;
        }
        pin(acc);
        const uint32_t alo = (smd + ((OFF_A + wg * 8192) >> 4)) | LBO1, blo = (smd + (OFF_B >> 4)) | LBO8K;
        mainloop<14, IA_U, IB_W2, 2>(bar0, alo, blo, leader, wg, LAG2, [&](uint64_t a, uint64_t b) { wgmma_ss_bf16_n128<0, 1>(acc, a, b, 1); });
        mbar_wait(bar0 + 8 * BAR_WD, 1);
        wg_wait<0>();
        pin(acc);
        if (leader) STAMP(wg ? 48 : 9);
        xsend<32, 4>(acc, peer + OFF_X + XB + warp * 2048 + lane * 16, peer + OFF_BAR + 8 * (BAR_XC + warp));
        float eo[32];
#pragma unroll
        for (int i = 0; i < 32; i++) eo[i] = 0.f;
        pin(eo);
        mainloop<4, IA_C, IB_Z, 2>(bar0, alo, blo + wg * 512, false, wg, 0, [&](uint64_t a, uint64_t b) { wgmma_ss_bf16_n64<0, 1>(eo, a, b, 1); });
        if (leader) STAMP(wg ? 49 : 40);
        mbar_wait(bar0 + 8 * BAR_XT, 0);
        const uint32_t xt = sm + OFF_X + wg * 8192;
        const uint32_t xa = xt + ((lane >> 4) * 8 + (lane & 7)) * 128 + (((2 * w + ((lane >> 3) & 1)) ^ (lane & 7)) << 4);
        const uint32_t eb = sm + OFF_B + ((IB_Z - 2) % SB) * SLOT + lane * 16;
        uint32_t xv[16], ep[16], gt[16];
#pragma unroll
        for (int i = 0; i < 4; i++) ldsm4t(xa + i * 2048, xv[4 * i], xv[4 * i + 1], xv[4 * i + 2], xv[4 * i + 3]);
        mbar_wait(bar0 + 8 * (BAR_EB + (IB_Z - 2) % SB), ((IB_Z - 2) / SB) & 1);
        wg_wait<0>();
        pin(eo);
        if (tid == 0) STAMP(10);
#pragma unroll
        for (int i = 0; i < 16; i++) ep[i] = pk_b(eo[2 * i], eo[2 * i + 1]);
#pragma unroll
        for (int i = 0; i < 4; i++) sts128(eb + warp * 2048 + i * 512, ep[4 * i], ep[4 * i + 1], ep[4 * i + 2], ep[4 * i + 3]);
        bar_arrive(13 + wg, 256);
        mbar_wait(bar0 + 8 * (BAR_XC + warp), 1);
        if (leader) STAMP(wg ? 50 : 21);
#pragma unroll
        for (int i = 0; i < 4; i++) { const uint4 p = lds128(xw + XB + i * 512 + lane * 16); gt[4 * i] = p.x; gt[4 * i + 1] = p.y; gt[4 * i + 2] = p.z; gt[4 * i + 3] = p.w; }
        bar_sync(14 - wg, 256);
        if (tid == 0) STAMP(45);
        const uint32_t sg = wg ? 0xbf80bf80u : 0x3f803f80u;
#pragma unroll
        for (int i = 0; i < 4; i++) {
            const uint4 p = lds128(eb + (warp ^ 4) * 2048 + i * 512);
            ep[4 * i] = fma_b2(ep[4 * i], sg, p.x); ep[4 * i + 1] = fma_b2(ep[4 * i + 1], sg, p.y);
            ep[4 * i + 2] = fma_b2(ep[4 * i + 2], sg, p.z); ep[4 * i + 3] = fma_b2(ep[4 * i + 3], sg, p.w);
        }
#pragma unroll
        for (int hf = 0; hf < NH; hf++) {
#pragma unroll
            for (int jj = 0; jj < 16 / NH; jj++) {
                const int j = hf * (16 / NH) + jj;
                const float h0 = acc[2 * j] + bf_lo(gt[j]), h1 = acc[2 * j + 1] + bf_hi(gt[j]);
                xv[j] = fma_b2(ep[j], pk_b(fmaf(h0, tanh_fast(h0), h0), fmaf(h1, tanh_fast(h1), h1)), xv[j]);
            }
#pragma unroll
            for (int ii = 0; ii < 4 / NH; ii++) { const int i = hf * (4 / NH) + ii; stsm4t(xa + i * 2048, xv[4 * i], xv[4 * i + 1], xv[4 * i + 2], xv[4 * i + 3]); }
            bar_arrive(hf ? 6 + wg : 10 + wg, 160);
            if (hf + 1 < NH) mbar_wait(bar0 + 8 * BAR_XT, 0);
        }
        if (tid == 0) STAMP(46);
    } else {
        asm volatile("setmaxnreg.dec.sync.aligned.u32 72;");
        bar_sync(15, 128);
        if (nog1) {
            if (warp == 8 && lane < 24) mbar_init(bar0 + 8 * (BAR_RF + lane), lane < 12 ? 1 : 9);
            if (warp == 9 && (lane >= 24 || lane % 6 < 4))
                asm volatile("mbarrier.arrive.shared::cta.b64 _, [%0], %1;" :: "r"(bar0 + 8 * lane), "r"(lane < 24 ? 1 + ((lane / 6) & 1) : 1) : "memory");
            __syncwarp();
        }
        {
            const int g = lane >> 2, t = lane & 3, A = 4 * (4 * t + warp - 8) * g;
            sts128f(sm + OFF_FR + (1 + warp) * 512 + lane * 16, cos2048(A), cos2048(A + 512), cos2048(A + 64 * g), cos2048(A + 64 * g + 512));
            const int i = warp - 8, R0 = (i & 1) && g == 0 ? 1024 : 128 * g, A0 = (t + 8 * (i >> 1)) * R0 + ((i & 1) && g ? 512 : 0);
            sts32(sm + OFF_FR + lane * 16 + i * 4, pk_h(cos2048(A0), cos2048(A0 + 4 * R0)));
            __syncwarp();
            mbar_arrive_p(bar0 + 8 * BAR_FR, lane == 0);
        }
        if (warp == 8) {
            if (!spare && elect()) {
#pragma unroll 1
                for (int j = 0; j < N_PF; j++) {
                    wait_until(t0, T_PF + j * SLOT_PF);
                    bulk_pf(w1 + (size_t)(rank * 1024 + j * 128 + (cid >> 1)) * 1792, 3584);
                }
            }
            __syncwarp();
            if (nog1 && elect()) {
                if (!spare) mbar_wait(bar0 + 8 * BAR_HF, 0); else wait_until(t0, T_WK);
                STAMP(18);
#pragma unroll 1
                for (int n = 0; n < nrec + W_AHEAD; n++) {
                    if (n >= W_AHEAD) {
                        mbar_wait(bar0 + 8 * (BAR_RD + n - W_AHEAD), 0);
                        asm volatile("fence.proxy.async.shared::cta;" ::: "memory");
                        tma3d_st(&M.ws, sm + (n - W_AHEAD) * WIMG, 0, 0, 2 * (rec0 + n - W_AHEAD) + 1);
                    }
                    if (n < nrec) {
                        const int rec = rec0 + n;
                        mbar_expect(bar0 + 8 * (BAR_RF + n), 16896);
                        tma4d(sm + n * WIMG, &M.wr, bar0 + 8 * (BAR_RF + n), 128 * ((rec >> 2) & 7), rec >> 5, 4 * (rec & 3), 0);
                        tma4d(sm + n * WIMG + 8448, &M.wi, bar0 + 8 * (BAR_RF + n), 128 * ((rec >> 2) & 7), rec >> 5, 4 * (rec & 3), 0);
                    }
                }
                asm volatile("cp.async.bulk.commit_group;" ::: "memory");
                asm volatile("cp.async.bulk.wait_group 0;" ::: "memory");
                mbar_arrive_p(bar0 + 8 * BAR_WI, true);
                STAMP(15);
            }
            __syncwarp();
            if (!spare && elect()) {
                Ring<SB, BAR_FB, BAR_EB, OFF_B> r(sm, nog1 ? 16 : 0);
                uint32_t tn = 0;
                if (!nog1) {
                    mbar_wait(bar0 + 8 * (B_GATE ? BAR_HF : BAR_HA), 0);
#pragma unroll 1
                    for (int i = 0; i < 16; i++) {
                        r.acquire(16384);
                        if (i == NB_EARLY) { mbar_wait(bar0 + 8 * BAR_GO, 0); tn = clk() + B_OFS; }
                        if (i >= NB_EARLY && i < SB) { while ((int)(clk() - tn) < 0) {} tn += PACE_F; }
                        tma3d(r.dst(), &M.w1, r.full(), 0, rank * 1024 + (i & 7) * 128 + (i >> 3) * 64, f0 >> 6);
                        r.next();
                    }
                }
                if (GATE_W2 || nog1) mbar_wait(bar0 + 8 * BAR_YR, 0);
                tn = clk();
#pragma unroll 1
                for (int j = 0; j < 14; j++) {
                    const int row = rank * 896 + (j < 7 ? 128 * j : 128 * j - 832);
                    if (j == NW2 && !nog1) { mbar_wait(bar0 + 8 * BAR_UG, 0); tn = clk(); }
                    while ((int)(clk() - tn) < 0) {}
                    tn += PACE_B;
                    r.acquire(16384);
                    tma2d(r.dst(), &M.w2, r.full(), s_own, row);
                    tma2d(r.dst() + 8192, &M.w2, r.full(), s_for, row);
                    r.next();
                }
                mbar_expect(bar0 + 8 * BAR_XT, 16384);
                tma3d(sm + OFF_X, &M.x, bar0 + 8 * BAR_XT, dblk * 64, s_own, 0);
                poll_ge(cnt + CNT_Z, 129);
                STAMP(16);
#pragma unroll 1
                for (int row = 0; row < 256; row += 64) {
                    r.acquire(16384);
                    tma3d(r.dst(), &M.z, r.full(), s_own, row, 0);
                    r.next();
                }
                if (atomicAdd(cnt + CNT_DONE, 1) == 127) {
                    for (int i = 0; i < CNT_WORDS; i += 32) cnt[i] = 0;
                }
            }
        } else if (warp == 9) {
            if (nog1 && !spare) {
                bar_sync(12, 288);
                if (elect()) red_release(cnt + CNT_Y);
                __syncwarp();
            }
            if ((!spare || cid == 0) && elect()) {
                Ring<SA, BAR_FA, BAR_EA, OFF_A> r(sm, nog1 ? 16 : 0);
                if (nog1) mbar_wait(bar0 + 8 * BAR_YR, 0);
                else {
                    uint32_t tn = 0;
#pragma unroll 1
                    for (int i = 0; i < 16; i++) {
                        r.acquire(16384);
                        if (i == 0 || i == 8) { poll_ge(cnt + CNT_H + (i || ONE_H ? 64 : 0) + 32 * rank, 64); if (i) STAMP(22); }
                        else if (i < SA) { while ((int)(clk() - tn) < 0) {} tn += PACE_F; }
                        tma3d(r.dst(), &M.h, r.full(), dblk * 64, rank * 1024 + (i & 7) * 128 + (i >> 3) * 64, 0);
                        if (i == 0) { tn = clk() + PACE_F; mbar_arrive_p(bar0 + 8 * BAR_GO, true); STAMP(12); }
                        r.next();
                    }
                }
#pragma unroll 1
                for (int i = 16; i < 20; i++) {
                    r.acquire(16384);
                    if (i == IA_Y || i == IA_W) { poll_ge(cnt + (i == IA_Y ? CNT_Y : CNT_T), i == IA_Y ? 144 : 20); STAMP(i == IA_Y ? 13 : 26); }
                    if (i == IA_C0 || i == IA_C1) bulk1d(r.dst(), S_.T + (i - IA_C0) * 8192, 16384, r.full());
                    else tma2d(r.dst(), &M.y, r.full(), (i == IA_W ? 8256 : 0) + (spare ? 8192 : i == IA_W ? cid * 64 : ygrp(cid) * 64), 0);
                    r.next();
                }
                if (!spare) {
#pragma unroll 1
                    for (int j = 0; j < 14; j++) {
                        r.acquire(16384);
                        if (j == 0 || j == 7) { poll_ge(cnt + (j || ONE_U ? CNT_U : CNT_V) + 32 * (dblk + 4 * rank), 14); STAMP(j ? 28 : 14); }
                        tma3d(r.dst(), &M.ul, r.full(), rank * 896 + (j < 7 ? 128 * j : 128 * j - 832), dblk * 64, 0);
                        mbar_arrive_p(bar0 + 8 * BAR_UG, j == 0);
                        r.next();
                    }
                    poll_ge(cnt + CNT_W, 4);
#pragma unroll 1
                    for (int col = 0; col < 256; col += 64) {
                        r.acquire(16384);
                        tma3d(r.dst(), &M.c, r.full(), col, dblk * 64, 0);
                        r.next();
                    }
                }
            }
        } else if (warp == 10) {
            if (!spare) {
                if (lane == 0) STAMP(56);
                bar_sync(2, 288);
                if (lane == 0) STAMP(44);
                if (elect()) { if (!ONE_H) red_release(cnt + CNT_H + 32 * (cid >> 6), WEAK & 1); STAMP(17); mbar_arrive_p(bar0 + 8 * BAR_HA, true); }
                __syncwarp();
            }
            if (nog1) { mbar_wait(bar0 + 8 * BAR_FR, 0); w_records(sm, rec0, nrec, lane & 1, 128, lane < 2, lane); }
            if (!nog1) {
                bar_sync(2, 288);
                if (elect()) { if (!ONE_U) red_release(cnt + CNT_V + 32 * (dblk + (f0 >= 896 ? 4 : 0))); STAMP(41); }
                __syncwarp();
            }
            if (spare) {
                bar_sync(4, 288);
                if (elect()) red_release(cnt + CNT_W);
            }
        } else {
            if (!spare) {
                if (cid < 2) asm volatile("prefetch.global.L2 [%0];" :: "l"(cid ? b2 + lane * 64 : b1 + min(lane, 27) * 64));
                bar_sync(9, 288);
                if (elect()) { red_release(cnt + CNT_H + 64 + 32 * (cid >> 6)); STAMP(23); mbar_arrive_p(bar0 + 8 * BAR_HF, true); }
                __syncwarp();
                bar_sync(4, 288);
            }
            if (elect()) {
                if (!spare) {
                    mbar_wait(bar0 + 8 * (nog1 ? BAR_HF : BAR_GO), 0);
                    asm volatile("fence.proxy.async.shared::cta;" ::: "memory");
                    uint32_t tn = clk() + (nog1 ? WKY : T_Y);
#pragma unroll 1
                    for (int q = 0; q < 9; q++) {
                        while ((int)(clk() - tn) < 0) {}
                        tn += q != 7 && !nog1 ? PACE_ST : 0;
                        tma3d_st(&M.ys, sm + OFF_X + q * 2048, 0, q * 16, 2 * cid);
                    }
                    asm volatile("cp.async.bulk.commit_group;" ::: "memory");
                    asm volatile("cp.async.bulk.wait_group 0;" ::: "memory");
                    STAMP(27);
                    uint32_t pb; asm("mapa.shared::cluster.u32 %0, %1, %2;" : "=r"(pb) : "r"(bar0 + 8 * BAR_WD), "r"(rank ^ 1));
                    asm volatile("mbarrier.arrive.shared::cluster.b64 _, [%0];" :: "r"(pb) : "memory");
                    mbar_arrive_p(bar0 + 8 * BAR_WD, true);
                }
                if (!spare) { red_release(cnt + CNT_Y, WEAK & 4); STAMP(24); }
                if (nog1) { mbar_wait(bar0 + 8 * BAR_WI, 0); red_release(cnt + CNT_T); }
                mbar_arrive_p(bar0 + 8 * BAR_YR, true);
            }
            __syncwarp();
            if (!nog1) {
                bar_sync(5, 288);
                if (elect()) { red_release(cnt + CNT_U + 32 * (dblk + (f0 >= 896 ? 4 : 0)), WEAK & 2); STAMP(19); }
                __syncwarp();
            }
            if (!spare || cid == 0) {
                bar_sync(8, spare ? 160 : 288);
                if (elect()) {
                    asm volatile("fence.proxy.async.shared::cta;" ::: "memory");
                    uint32_t tn = clk();
#pragma unroll 1
                    for (int p = 0; p < (spare ? 2 : 8); p++) {
                        if (cid == 0 && (p == 2 || p == 3)) continue;
                        while ((int)(clk() - tn) < 0) {}
                        tn += PACE_Z;
                        asm volatile("cp.async.bulk.global.shared::cta.bulk_group [%0], [%1], 2048;"
                                     :: "l"(S_.Z + (spare ? 2048 : (p >> 2) * (256 * 2048) + cid * 4096) + (p & 3) * 1024), "r"(sm + OFF_X + XB + p * 2048) : "memory");
                    }
                    asm volatile("cp.async.bulk.commit_group;" ::: "memory");
                    asm volatile("cp.async.bulk.wait_group 0;" ::: "memory");
                    if (!spare) {
                        uint32_t pb; asm("mapa.shared::cluster.u32 %0, %1, %2;" : "=r"(pb) : "r"(bar0 + 8 * BAR_WD), "r"(rank ^ 1));
                        asm volatile("mbarrier.arrive.shared::cluster.b64 _, [%0];" :: "r"(pb) : "memory");
                        mbar_arrive_p(bar0 + 8 * BAR_WD, true);
                    }
                    red_release(cnt + CNT_Z, WEAK & 8); STAMP(25);
                }
                __syncwarp();
            }
        }
        if (warp >= 10 && !spare) {
            const int wg = warp - 10;
#pragma unroll
            for (int hf = 0; hf < NH; hf++) {
                bar_sync(hf ? 6 + wg : 10 + wg, 160);
                if (elect()) {
                    asm volatile("fence.proxy.async.shared::cta;" ::: "memory");
                    tma3d_st(&M.o, sm + OFF_X + wg * 8192 + hf * (8192 / NH), dblk * 64, s_own + hf * (64 / NH), wg);
                    asm volatile("cp.async.bulk.commit_group;" ::: "memory");
                    if (hf + 1 == NH) {
                        if (wg == 0) STAMP(47);
                        asm volatile("cp.async.bulk.wait_group.read 0;" ::: "memory");
                    }
                }
                __syncwarp();
            }
        }
    }
}

typedef CUresult (*EncodeFn)(CUtensorMap*, CUtensorMapDataType, cuuint32_t, void*, const cuuint64_t*, const cuuint64_t*, const cuuint32_t*,
                             const cuuint32_t*, CUtensorMapInterleave, CUtensorMapSwizzle, CUtensorMapL2promotion, CUtensorMapFloatOOBfill);

void make_map(EncodeFn enc, CUtensorMap* m, const void* p, int rank, cuuint64_t d0, cuuint64_t d1, cuuint64_t d2, cuuint64_t s1, cuuint64_t s2,
              cuuint32_t b0, cuuint32_t b1, cuuint32_t b2) {
    cuuint64_t gd[3] = {d0, d1, d2}, gs[2] = {s1, s2};
    cuuint32_t bx[3] = {b0, b1, b2}, es[3] = {1, 1, 1};
    enc(m, CU_TENSOR_MAP_DATA_TYPE_BFLOAT16, rank, const_cast<void*>(p), gd, gs, bx, es, CU_TENSOR_MAP_INTERLEAVE_NONE,
        CU_TENSOR_MAP_SWIZZLE_128B, CU_TENSOR_MAP_L2_PROMOTION_L2_128B, CU_TENSOR_MAP_FLOAT_OOB_FILL_NONE);
}

}

extern "C" void kernel_launch(void* const* d_in, const int* in_sizes, int n_in, void* d_out, int out_size) {
    (void)in_sizes; (void)n_in; (void)out_size;
    const __nv_bfloat16* x = (const __nv_bfloat16*)d_in[0];
    const __nv_bfloat16* wr = (const __nv_bfloat16*)d_in[1];
    const __nv_bfloat16* wi = (const __nv_bfloat16*)d_in[2];
    const __nv_bfloat16* w1 = (const __nv_bfloat16*)d_in[4];
    const __nv_bfloat16* b1 = (const __nv_bfloat16*)d_in[5];
    const __nv_bfloat16* w2 = (const __nv_bfloat16*)d_in[6];
    const __nv_bfloat16* b2 = (const __nv_bfloat16*)d_in[7];
    EncodeFn enc = nullptr;
    cudaDriverEntryPointQueryResult qr;
    cudaGetDriverEntryPoint("cuTensorMapEncodeTiled", (void**)&enc, cudaEnableDefault, &qr);
    Scratch* s = nullptr;
    cudaGetSymbolAddress((void**)&s, g_s);
    cudaFuncSetAttribute(fused_kernel, cudaFuncAttributeMaxDynamicSharedMemorySize, SMEM_BYTES);
    Maps M;
    make_map(enc, &M.h, s->h, 3, 256, 2048, 2, 1024, 512, 64, 64, 2);
    make_map(enc, &M.w1, w1, 3, 64, 2048, 28, 3584, 128, 64, 64, 2);
    make_map(enc, &M.y, s->Y, 2, YPITCH, 128, 1, YPITCH * 2, 0, 64, 128, 1);
    make_map(enc, &M.ws, s->Y, 3, 64, 129, 256, 128, YPITCH, 64, 129, 1);
    make_map(enc, &M.ys, s->Y, 3, 64, 129, 256, 128, YPITCH, 64, 16, 1);
    make_map(enc, &M.ul, s->u, 3, 1792, 256, 2, 3584, 3584 * 256, 64, 64, 2);
    make_map(enc, &M.w2, w2, 2, 2048, 1792, 1, 4096, 0, 64, 64, 1);
    make_map(enc, &M.c, s->C, 3, 256, 256, 2, 512, 131072, 64, 64, 2);
    make_map(enc, &M.z, s->Z, 3, 2048, 256, 2, 4096, 1048576, 64, 64, 2);
    make_map(enc, &M.x, x, 3, 256, 2048, 2, 1024, 512, 64, 64, 2);
    make_map(enc, &M.o, d_out, 3, 256, 2048, 2, 1024, 512, 64, 64 / NH, 1);
    for (int i = 0; i < 2; i++) {
        cuuint64_t gd[4] = {1028, 4, 16, 4}, gs[3] = {4112, 16448, 263168};
        cuuint32_t bx[4] = {132, 1, 4, 4}, es[4] = {1, 1, 1, 1};
        enc(i ? &M.wi : &M.wr, CU_TENSOR_MAP_DATA_TYPE_UINT32, 4, (void*)(i ? wi : wr), gd, gs, bx, es, CU_TENSOR_MAP_INTERLEAVE_NONE,
            CU_TENSOR_MAP_SWIZZLE_NONE, CU_TENSOR_MAP_L2_PROMOTION_L2_128B, CU_TENSOR_MAP_FLOAT_OOB_FILL_NONE);
    }
    fused_kernel<<<132, 384, SMEM_BYTES, cudaStreamPerThread>>>(x, s, TUNE_ARG w1, b1, b2, M);
}
```
